```python
import torch

def _softmax(x, axis=-1):
    return torch.softmax(x, dim=axis)
def _gelu(x):
    return torch.nn.functional.gelu(x, approximate="tanh")
def _silu(x):
    return torch.nn.functional.silu(x)
def _sigmoid(x):
    return torch.sigmoid(x)
def _layernorm(x, axis=-1, eps=1e-5):
    m = x.mean(dim=axis, keepdim=True)
    v = x.var(dim=axis, keepdim=True, unbiased=False)
    return (x - m) / torch.sqrt(v + eps)
def _scatter_add(tgt, idx, src, axis=0):
    return tgt.clone().index_add_(axis, idx, src)
def _segment_sum(src, seg, n):
    out = torch.zeros((n,) + src.shape[1:], dtype=src.dtype)
    return out.index_add_(0, seg, src)
def _pad(x, pw):
    flat = tuple(v for pair in reversed(pw) for v in pair)
    return torch.nn.functional.pad(x, flat)

kernel_name = 'standalone__gqa_softmax__near_ridge'

def setup_inputs():

    _w = (lambda a: (lambda t: t.to(torch.bfloat16) if t.is_floating_point() else t)(torch.as_tensor(a)))
    B, Hq, Hkv, Sq, Sk, D = 16, 32, 8, 512, 512, 128
    return {
        "q": _w((lambda *s: torch.randn(*s, dtype=torch.bfloat16) * 0.8)(B, Hq, Sq, D)),
        "k": _w((lambda *s: torch.randn(*s, dtype=torch.bfloat16) * 0.8)(B, Hkv, Sk, D)),
        "v": _w((lambda *s: torch.randn(*s, dtype=torch.bfloat16) * 0.05)(B, Hkv, Sk, D)),
    }

def reference(q, k, v):
    B, Hq, Sq, D = q.shape
    Hkv = k.shape[1]
    rep = Hq // Hkv
    k = (lambda x, n, axis: torch.repeat_interleave(x, n, dim=axis))(k, rep, axis=1)
    v = (lambda x, n, axis: torch.repeat_interleave(x, n, dim=axis))(v, rep, axis=1)
    scale = D ** -0.5
    scores = torch.einsum("bhqd,bhkd->bhqk", q, k) * scale
    p = _softmax(scores, axis=-1)
    return torch.einsum("bhqk,bhkd->bhqd", p, v)
```

```cpp
#include <cuda_runtime.h>
#include <cuda_bf16.h>
#include <cuda.h>
#include <stdint.h>
#include <type_traits>

#define CLUSTER 2
#define Q_IN_REGS 0
#define PINGPONG 1
#define NUM_CTAS 128
#define JSPLIT 10
#define QPREFETCH 0
#define EPI_SPLIT 4
#define PRE0 0
#define PREFETCH 1

namespace {

constexpr int D_HEAD = 128;
constexpr int SK = 512;
constexpr int BM = 128;
constexpr int BN = 128;
constexpr int NBLK = SK / BN;
constexpr int ROWS_PER_PAIR = 2048;
constexpr int NPAIRS = 128;
constexpr int TILES_PER_PAIR = ROWS_PER_PAIR / BM;
constexpr int NTILES = NPAIRS * TILES_PER_PAIR;
constexpr int STAGES = 5;
constexpr int STAGE_BYTES = BN * D_HEAD * 2;
constexpr int QBUF_BYTES = BM * D_HEAD * 2;
constexpr int SMEM_Q = 0;
constexpr int SMEM_KV = 2 * QBUF_BYTES;
constexpr int SMEM_BAR = SMEM_KV + STAGES * STAGE_BYTES;
constexpr int SMEM_TOTAL = SMEM_BAR + 256 + 1024;
constexpr int NTHREADS = 384;

__device__ __forceinline__ uint32_t smem_u32(const void* p) { return (uint32_t)__cvta_generic_to_shared(p); }

__device__ __forceinline__ void mbar_init(uint32_t bar, uint32_t count) {
    asm volatile("mbarrier.init.shared::cta.b64 [%0], %1;\n" :: "r"(bar), "r"(count) : "memory");
}
__device__ __forceinline__ void mbar_expect_tx(uint32_t bar, uint32_t bytes) {
    asm volatile("mbarrier.arrive.expect_tx.shared::cta.b64 _, [%0], %1;\n" :: "r"(bar), "r"(bytes) : "memory");
}
__device__ __forceinline__ void mbar_arrive_cluster(uint32_t bar, uint32_t cta) {
    asm volatile("{\n.reg .b32 ra;\nmapa.shared::cluster.u32 ra, %0, %1;\n"
                 "mbarrier.arrive.shared::cluster.b64 _, [ra];\n}\n" :: "r"(bar), "r"(cta) : "memory");
}
__device__ __forceinline__ void mbar_arrive_local(uint32_t bar) {
    asm volatile("mbarrier.arrive.shared::cta.b64 _, [%0];\n" :: "r"(bar) : "memory");
}
__device__ __forceinline__ void mbar_wait(uint32_t bar, uint32_t parity) {
    asm volatile("{\n.reg .pred p, q;\n.reg .u32 c;\nmov.u32 c, 0;\n"
                 "LAB_WAIT:\n"
                 "mbarrier.try_wait.parity.shared::cta.b64 p, [%0], %1;\n"
                 "@p bra LAB_DONE;\n"
                 "add.u32 c, c, 1;\n"
                 "setp.gt.u32 q, c, 16777216;\n"
                 "@q trap;\n"
                 "bra LAB_WAIT;\n"
                 "LAB_DONE:\n}\n" :: "r"(bar), "r"(parity) : "memory");
}
__device__ __forceinline__ uint32_t mbar_test(uint32_t bar, uint32_t parity) {
    uint32_t ok;
    asm volatile("{\n.reg .pred p;\nmbarrier.test_wait.parity.shared::cta.b64 p, [%1], %2;\nselp.u32 %0, 1, 0, p;\n}\n"
                 : "=r"(ok) : "r"(bar), "r"(parity) : "memory");
    return ok;
}
__device__ __forceinline__ void mbar_wait_cluster(uint32_t bar, uint32_t parity) {
    asm volatile("{\n.reg .pred p, q;\n.reg .u32 c;\nmov.u32 c, 0;\n"
                 "LAB_WAIT:\n"
                 "mbarrier.try_wait.parity.acquire.cluster.shared::cta.b64 p, [%0], %1;\n"
                 "@p bra LAB_DONE;\n"
                 "add.u32 c, c, 1;\n"
                 "setp.gt.u32 q, c, 16777216;\n"
                 "@q trap;\n"
                 "bra LAB_WAIT;\n"
                 "LAB_DONE:\n}\n" :: "r"(bar), "r"(parity) : "memory");
}

__device__ __forceinline__ void tma_load_2d(uint32_t dst, const CUtensorMap* map, int c0, int c1, uint32_t bar) {
    asm volatile("cp.async.bulk.tensor.2d.shared::cluster.global.mbarrier::complete_tx::bytes [%0], [%1, {%3, %4}], [%2];\n"
                 :: "r"(dst), "l"(map), "r"(bar), "r"(c0), "r"(c1) : "memory");
}
__device__ __forceinline__ void tma_load_2d_mc(uint32_t dst, const CUtensorMap* map, int c0, int c1, uint32_t bar, uint16_t mask) {
    asm volatile("cp.async.bulk.tensor.2d.shared::cluster.global.mbarrier::complete_tx::bytes.multicast::cluster [%0], [%1, {%3, %4}], [%2], %5;\n"
                 :: "r"(dst), "l"(map), "r"(bar), "r"(c0), "r"(c1), "h"(mask) : "memory");
}
__device__ __forceinline__ void tma_store_2d(const CUtensorMap* map, uint32_t src, int c0, int c1) {
    asm volatile("cp.async.bulk.tensor.2d.global.shared::cta.bulk_group [%0, {%2, %3}], [%1];\n"
                 :: "l"(map), "r"(src), "r"(c0), "r"(c1) : "memory");
}
__device__ __forceinline__ void tma_prefetch_2d(const CUtensorMap* map, int c0, int c1) {
    asm volatile("cp.async.bulk.prefetch.tensor.2d.L2.global [%0, {%1, %2}];\n"
                 :: "l"(map), "r"(c0), "r"(c1) : "memory");
}

__device__ __forceinline__ uint64_t make_desc(uint32_t addr, uint32_t lbo, uint32_t sbo) {
    uint64_t d = 0;
    d |= (uint64_t)((addr & 0x3FFFF) >> 4);
    d |= (uint64_t)((lbo >> 4) & 0x3FFF) << 16;
    d |= (uint64_t)((sbo >> 4) & 0x3FFF) << 32;
    d |= (uint64_t)1 << 62;
    return d;
}

#define WG_FENCE() asm volatile("wgmma.fence.sync.aligned;\n" ::: "memory")
#define WG_COMMIT() asm volatile("wgmma.commit_group.sync.aligned;\n" ::: "memory")
#define WG_WAIT(n) asm volatile("wgmma.wait_group.sync.aligned " #n ";\n" ::: "memory")

#define ACC64(d) \
  "+f"(d[0]), "+f"(d[1]), "+f"(d[2]), "+f"(d[3]), "+f"(d[4]), "+f"(d[5]), "+f"(d[6]), "+f"(d[7]), \
  "+f"(d[8]), "+f"(d[9]), "+f"(d[10]), "+f"(d[11]), "+f"(d[12]), "+f"(d[13]), "+f"(d[14]), "+f"(d[15]), \
  "+f"(d[16]), "+f"(d[17]), "+f"(d[18]), "+f"(d[19]), "+f"(d[20]), "+f"(d[21]), "+f"(d[22]), "+f"(d[23]), \
  "+f"(d[24]), "+f"(d[25]), "+f"(d[26]), "+f"(d[27]), "+f"(d[28]), "+f"(d[29]), "+f"(d[30]), "+f"(d[31]), \
  "+f"(d[32]), "+f"(d[33]), "+f"(d[34]), "+f"(d[35]), "+f"(d[36]), "+f"(d[37]), "+f"(d[38]), "+f"(d[39]), \
  "+f"(d[40]), "+f"(d[41]), "+f"(d[42]), "+f"(d[43]), "+f"(d[44]), "+f"(d[45]), "+f"(d[46]), "+f"(d[47]), \
  "+f"(d[48]), "+f"(d[49]), "+f"(d[50]), "+f"(d[51]), "+f"(d[52]), "+f"(d[53]), "+f"(d[54]), "+f"(d[55]), \
  "+f"(d[56]), "+f"(d[57]), "+f"(d[58]), "+f"(d[59]), "+f"(d[60]), "+f"(d[61]), "+f"(d[62]), "+f"(d[63])
#define OUT64(d) \
  "=f"(d[0]), "=f"(d[1]), "=f"(d[2]), "=f"(d[3]), "=f"(d[4]), "=f"(d[5]), "=f"(d[6]), "=f"(d[7]), \
  "=f"(d[8]), "=f"(d[9]), "=f"(d[10]), "=f"(d[11]), "=f"(d[12]), "=f"(d[13]), "=f"(d[14]), "=f"(d[15]), \
  "=f"(d[16]), "=f"(d[17]), "=f"(d[18]), "=f"(d[19]), "=f"(d[20]), "=f"(d[21]), "=f"(d[22]), "=f"(d[23]), \
  "=f"(d[24]), "=f"(d[25]), "=f"(d[26]), "=f"(d[27]), "=f"(d[28]), "=f"(d[29]), "=f"(d[30]), "=f"(d[31]), \
  "=f"(d[32]), "=f"(d[33]), "=f"(d[34]), "=f"(d[35]), "=f"(d[36]), "=f"(d[37]), "=f"(d[38]), "=f"(d[39]), \
  "=f"(d[40]), "=f"(d[41]), "=f"(d[42]), "=f"(d[43]), "=f"(d[44]), "=f"(d[45]), "=f"(d[46]), "=f"(d[47]), \
  "=f"(d[48]), "=f"(d[49]), "=f"(d[50]), "=f"(d[51]), "=f"(d[52]), "=f"(d[53]), "=f"(d[54]), "=f"(d[55]), \
  "=f"(d[56]), "=f"(d[57]), "=f"(d[58]), "=f"(d[59]), "=f"(d[60]), "=f"(d[61]), "=f"(d[62]), "=f"(d[63])
#define REGS64 \
  "{%0, %1, %2, %3, %4, %5, %6, %7, %8, %9, %10, %11, %12, %13, %14, %15, " \
  "%16, %17, %18, %19, %20, %21, %22, %23, %24, %25, %26, %27, %28, %29, %30, %31, " \
  "%32, %33, %34, %35, %36, %37, %38, %39, %40, %41, %42, %43, %44, %45, %46, %47, " \
  "%48, %49, %50, %51, %52, %53, %54, %55, %56, %57, %58, %59, %60, %61, %62, %63}"

__device__ __forceinline__ void fence_regs(float (&d)[64]) { asm volatile("" : ACC64(d) :: "memory"); }

template <int SCALE_D>
__device__ __forceinline__ void wgmma_ss(float (&d)[64], uint32_t da_lo, uint32_t db_lo) {
    if constexpr (SCALE_D) {
        asm volatile("{\n.reg .b64 da, db;\nmov.b64 da, {%64, %66};\nmov.b64 db, {%65, %66};\n"
                     "wgmma.mma_async.sync.aligned.m64n128k16.f32.bf16.bf16 " REGS64 ", da, db, 1, 1, 1, 0, 0;\n}\n"
                     : ACC64(d) : "r"(da_lo), "r"(db_lo), "r"(0x40000040));
    } else {
        asm volatile("{\n.reg .b64 da, db;\nmov.b64 da, {%64, %66};\nmov.b64 db, {%65, %66};\n"
                     "wgmma.mma_async.sync.aligned.m64n128k16.f32.bf16.bf16 " REGS64 ", da, db, 0, 1, 1, 0, 0;\n}\n"
                     : ACC64(d) : "r"(da_lo), "r"(db_lo), "r"(0x40000040));
    }
}
template <int SCALE_D, int TB>
__device__ __forceinline__ void wgmma_rs(float (&d)[64], uint32_t a0, uint32_t a1, uint32_t a2, uint32_t a3,
                                         uint32_t db_lo) {
    if constexpr (SCALE_D) {
        asm volatile("{\n.reg .b64 db;\nmov.b64 db, {%68, %70};\n"
                     "wgmma.mma_async.sync.aligned.m64n128k16.f32.bf16.bf16 " REGS64 ", {%64, %65, %66, %67}, db, 1, 1, 1, %69;\n}\n"
                     : ACC64(d) : "r"(a0), "r"(a1), "r"(a2), "r"(a3), "r"(db_lo), "n"(TB), "r"(0x40000040));
    } else {
        asm volatile("{\n.reg .b64 db;\nmov.b64 db, {%68, %70};\n"
                     "wgmma.mma_async.sync.aligned.m64n128k16.f32.bf16.bf16 " REGS64 ", {%64, %65, %66, %67}, db, 0, 1, 1, %69;\n}\n"
                     : ACC64(d) : "r"(a0), "r"(a1), "r"(a2), "r"(a3), "r"(db_lo), "n"(TB), "r"(0x40000040));
    }
}

template <int TB>
__device__ __forceinline__ void wgmma_rs_p(float (&d)[64], uint32_t a0, uint32_t a1, uint32_t a2, uint32_t a3,
                                           uint32_t db_lo, int scale_d) {
    asm volatile("{\n.reg .b64 db;\n.reg .pred p;\nsetp.ne.b32 p, %71, 0;\nmov.b64 db, {%68, %70};\n"
                 "wgmma.mma_async.sync.aligned.m64n128k16.f32.bf16.bf16 " REGS64 ", {%64, %65, %66, %67}, db, p, 1, 1, %69;\n}\n"
                 : ACC64(d) : "r"(a0), "r"(a1), "r"(a2), "r"(a3), "r"(db_lo), "n"(TB), "r"(0x40000040), "r"(scale_d));
}

__device__ __forceinline__ uint32_t pack_bf16(float lo, float hi) {
    uint32_t r;
    asm("cvt.rn.bf16x2.f32 %0, %1, %2;\n" : "=r"(r) : "f"(hi), "f"(lo));
    return r;
}
__device__ __forceinline__ float ex2(float x) {
    float y;
    asm("ex2.approx.ftz.f32 %0, %1;\n" : "=f"(y) : "f"(x));
    return y;
}
__device__ __forceinline__ float ex2v(float x) {
    float y;
    asm volatile("ex2.approx.ftz.f32 %0, %1;\n" : "=f"(y) : "f"(x));
    return y;
}
__device__ __forceinline__ void named_sync(int id, int n) { asm volatile("bar.sync %0, %1;\n" :: "r"(id), "r"(n) : "memory"); }
__device__ __forceinline__ void named_arrive(int id, int n) { asm volatile("bar.arrive %0, %1;\n" :: "r"(id), "r"(n) : "memory"); }

__device__ __forceinline__ void ldmatrix_x4(uint32_t& r0, uint32_t& r1, uint32_t& r2, uint32_t& r3, uint32_t addr) {
    asm volatile("ldmatrix.sync.aligned.m8n8.x4.shared.b16 {%0, %1, %2, %3}, [%4];\n"
                 : "=r"(r0), "=r"(r1), "=r"(r2), "=r"(r3) : "r"(addr) : "memory");
}
__device__ __forceinline__ void stmatrix_x4(uint32_t addr, uint32_t r0, uint32_t r1, uint32_t r2, uint32_t r3) {
    asm volatile("stmatrix.sync.aligned.m8n8.x4.shared.b16 [%0], {%1, %2, %3, %4};\n"
                 :: "r"(addr), "r"(r0), "r"(r1), "r"(r2), "r"(r3) : "memory");
}

#define STAMP(k)

#define SPANSTAMP(k)
#define PSTAMP(k)
template <int V> using IC = std::integral_constant<int, V>;

struct Ring {
    uint32_t stage, phase;
    __device__ __forceinline__ void advance() { if (++stage == STAGES) { stage = 0; phase ^= 1; } }
};

__global__ void __launch_bounds__(NTHREADS, 1)
gqa_attn_kernel(const __grid_constant__ CUtensorMap map_q, const __grid_constant__ CUtensorMap map_k,
                const __grid_constant__ CUtensorMap map_v, const __grid_constant__ CUtensorMap map_o) {
    extern __shared__ uint8_t smem_raw[];
    const uint32_t sbase = (smem_u32(smem_raw) + 1023u) & ~1023u;
    const uint32_t bar_base = sbase + SMEM_BAR;
    auto full_bar = [&](uint32_t s) { return bar_base + s * 8; };
    auto empty_bar = [&](uint32_t s) { return bar_base + 64 + s * 8; };
    auto qfull_bar = [&](uint32_t buf, uint32_t wg) { return bar_base + 128 + (buf * 2 + wg) * 8; };
    auto oready_bar = [&](uint32_t wg) { return bar_base + 160 + wg * 8; };

    const int tid = threadIdx.x;
    PSTAMP(0);
    const int wg_idx = __shfl_sync(0xffffffffu, tid >> 7, 0);
    uint32_t cta_rank = 0;
    asm volatile("mov.u32 %0, %%cluster_ctarank;\n" : "=r"(cta_rank));
    const int cluster_id = blockIdx.x / CLUSTER;
    const int num_clusters = gridDim.x / CLUSTER;
    constexpr int NCT = NTILES / CLUSTER;
    const int my_tiles = (NCT - cluster_id + num_clusters - 1) / num_clusters;

    auto q_smem = [&](int buf, int wg) { return sbase + SMEM_Q + buf * QBUF_BYTES + wg * 16384; };
    auto tile_row = [&](int i, int wg) {
        const int ct = cluster_id + i * num_clusters;
        return (ct * CLUSTER + (int)cta_rank) * BM + wg * 64;
    };
    auto load_q = [&](int i, int wg) {
        const int buf = i & 1;
        const uint32_t fb = qfull_bar(buf, wg);
        mbar_expect_tx(fb, 16384);
        tma_load_2d(q_smem(buf, wg), &map_q, 0, tile_row(i, wg), fb);
        tma_load_2d(q_smem(buf, wg) + 8192, &map_q, 64, tile_row(i, wg), fb);
    };

    auto prefetch_kv = [&](int ti) {
        if (ti < my_tiles) {
            const int nt = (cluster_id + ti * num_clusters) * CLUSTER + (int)cta_rank;
            const int idx = nt & (TILES_PER_PAIR - 1);
            tma_prefetch_2d((idx & 2) ? &map_v : &map_k, (idx & 1) * 64, (nt / TILES_PER_PAIR) * SK + (idx >> 2) * BN);
        }
    };

    if (tid == 256) {
        for (int s = 0; s < STAGES; s++) {
            mbar_init(full_bar(s), 1);
            mbar_init(empty_bar(s), 2 * CLUSTER);
        }
        for (int i = 0; i < 4; i++) mbar_init(bar_base + 128 + i * 8, 1);
        mbar_init(oready_bar(0), 128);
        mbar_init(oready_bar(1), 128);
        asm volatile("fence.mbarrier_init.release.cluster;\n" ::: "memory");
        asm volatile("fence.proxy.async.shared::cta;\n" ::: "memory");
        load_q(0, 0);
        const int row0 = ((cluster_id * CLUSTER) / TILES_PER_PAIR) * SK;
#pragma unroll 1
        for (int n = 0; n < STAGES; n++) {
            const bool is_v = (n == 2) || (n == 4);
            const CUtensorMap* map = is_v ? &map_v : &map_k;
            const int row = row0 + (is_v ? (n >> 1) - 1 : (n + 1) >> 1) * BN;
            mbar_expect_tx(full_bar(n), STAGE_BYTES);
            tma_load_2d(sbase + SMEM_KV + n * STAGE_BYTES, map, 0, row, full_bar(n));
            tma_load_2d(sbase + SMEM_KV + n * STAGE_BYTES + 16384, map, 64, row, full_bar(n));
            if (n == 0) load_q(0, 1);
        }
    } else if (tid == 320) {
        asm volatile("prefetch.tensormap [%0];\n" :: "l"(&map_k) : "memory");
        asm volatile("prefetch.tensormap [%0];\n" :: "l"(&map_v) : "memory");
        asm volatile("prefetch.tensormap [%0];\n" :: "l"(&map_o) : "memory");
    }
    PSTAMP(1);
    __syncthreads();
    PSTAMP(2);
    asm volatile("barrier.cluster.arrive.relaxed.aligned;\nbarrier.cluster.wait.aligned;\n" ::: "memory");
    PSTAMP(3);

    if (wg_idx == 2) {
        asm volatile("setmaxnreg.dec.sync.aligned.u32 24;\n");
        if (tid == 256) {
            const int G = my_tiles * NBLK;
            Ring ring{0, 0};
            auto load_kv = [&](const CUtensorMap* map, int g) {
                const int ct = cluster_id + (g >> 2) * num_clusters;
                const int pair = (ct * CLUSTER) / TILES_PER_PAIR;
                const int row = pair * SK + (g & 3) * BN;
                mbar_wait(empty_bar(ring.stage), ring.phase);
                const uint32_t fb = full_bar(ring.stage);
                mbar_expect_tx(fb, STAGE_BYTES);
                const uint32_t dst = sbase + SMEM_KV + ring.stage * STAGE_BYTES;
                tma_load_2d_mc(dst + cta_rank * 16384, map, cta_rank * 64, row, fb, (uint16_t)3);
                ring.advance();
            };
            for (int g = 3; g < G; g++) {
                load_kv(&map_k, g);
                if (g == 3 && my_tiles > 1) {
                    prefetch_kv(1);
                    load_q(1, 0);
                    load_q(1, 1);
                }
                load_kv(&map_v, g - 1);
                if ((g & 3) == PREFETCH) prefetch_kv((g >> 2) + 1);
            }
            load_kv(&map_v, G - 1);
            for (int s = 0; s < STAGES; s++) {
                mbar_wait(empty_bar(ring.stage), ring.phase);
                ring.advance();
            }
        } else if (tid == 288 || tid == 320) {
            const int wg = (tid - 288) >> 5;
            for (int i = 0; i < my_tiles; i++) {
                mbar_wait(oready_bar(wg), i & 1);
                tma_store_2d(&map_o, q_smem(i & 1, wg), 0, tile_row(i, wg));
                tma_store_2d(&map_o, q_smem(i & 1, wg) + 8192, 64, tile_row(i, wg));
                asm volatile("cp.async.bulk.commit_group;\n" ::: "memory");
                if (i + 2 < my_tiles) {
                    asm volatile("cp.async.bulk.wait_group.read 0;\n" ::: "memory");
                    load_q(i + 2, wg);
                }
            }
            asm volatile("cp.async.bulk.wait_group 0;\n" ::: "memory");
        }
    } else {
        asm volatile("setmaxnreg.inc.sync.aligned.u32 240;\n");
        const int wg = wg_idx;
        const int t = tid & 127;
        const int warp = t >> 5, lane = t & 31;
        const float c_log2 = 0.08838834764831845f * 1.4426950408889634f;
        const float SUM_HI = 1073741824.0f, SUM_LO = 1.0f / 1073741824.0f;

        auto release = [&](uint32_t stage) {
            if (t < CLUSTER) mbar_arrive_cluster(empty_bar(stage), t);
        };

        const int mrow = warp * 16 + (lane & 7) + ((lane >> 3) & 1) * 8;
        const uint32_t mat_off = mrow * 128;
        const uint32_t mat_x = (uint32_t)(lane >> 4);
        const uint32_t mat_sw = (uint32_t)(lane & 7);
        auto mat_addr = [&](uint32_t base, int kk) {
            return base + (kk >> 2) * 8192 + mat_off + ((((kk & 3) * 2 + mat_x) ^ mat_sw) << 4);
        };

        float s[64], o[64];
        uint32_t pa[32], pb[32];
        float m0 = 0.f, m1 = 0.f, l0 = 0.f, l1 = 0.f;
        float inv0 = 0.f, inv1 = 0.f;
        Ring ring{0, 0};
        const uint32_t kv_desc0 = ((sbase + SMEM_KV) & 0x3FFFF) >> 4;
        const uint32_t q_desc0 = ((q_smem(0, wg) & 0x3FFFF) >> 4) | (1u << 16);

        auto issue_qk = [&](uint32_t stage, int qbuf) {
            const uint32_t db = (kv_desc0 + stage * (STAGE_BYTES >> 4)) | (1u << 16);
            const uint32_t da = q_desc0 + qbuf * (QBUF_BYTES >> 4);
            WG_FENCE();
            wgmma_ss<0>(s, da, db);
#pragma unroll
            for (int kk = 1; kk < 8; kk++)
                wgmma_ss<1>(s, da + (kk >> 2) * 512 + (kk & 3) * 2, db + (kk >> 2) * 1024 + (kk & 3) * 2);
            WG_COMMIT();
        };
        auto issue_pv = [&](int accumulate, uint32_t stage, const uint32_t (&p)[32]) {
            const uint32_t db = (kv_desc0 + stage * (STAGE_BYTES >> 4)) | (1024u << 16);
            WG_FENCE();
            wgmma_rs_p<1>(o, p[0], p[1], p[2], p[3], db, accumulate);
#pragma unroll
            for (int kk = 1; kk < 8; kk++)
                wgmma_rs<1, 1>(o, p[kk * 4], p[kk * 4 + 1], p[kk * 4 + 2], p[kk * 4 + 3], db + kk * 128);
            WG_COMMIT();
        };
        auto row_max = [&](float& a0, float& a1) {
            a0 = fmaxf(s[0], s[1]); a1 = fmaxf(s[2], s[3]);
            float b0 = fmaxf(s[4], s[5]), b1 = fmaxf(s[6], s[7]);
#pragma unroll
            for (int j = 2; j < 16; j += 2) {
                a0 = fmaxf(a0, fmaxf(s[4 * j], s[4 * j + 1]));
                a1 = fmaxf(a1, fmaxf(s[4 * j + 2], s[4 * j + 3]));
                b0 = fmaxf(b0, fmaxf(s[4 * j + 4], s[4 * j + 5]));
                b1 = fmaxf(b1, fmaxf(s[4 * j + 6], s[4 * j + 7]));
            }
            a0 = fmaxf(a0, b0); a1 = fmaxf(a1, b1);
            a0 = fmaxf(a0, __shfl_xor_sync(0xffffffffu, a0, 1));
            a1 = fmaxf(a1, __shfl_xor_sync(0xffffffffu, a1, 1));
            a0 = fmaxf(a0, __shfl_xor_sync(0xffffffffu, a0, 2));
            a1 = fmaxf(a1, __shfl_xor_sync(0xffffffffu, a1, 2));
        };
        auto exp_pack = [&](uint32_t (&p)[32], float& r0, float& r1) {
            const float mc0 = m0 * c_log2, mc1 = m1 * c_log2;
            float x0 = 0.f, x1 = 0.f, x2 = 0.f, x3 = 0.f;
#pragma unroll
            for (int j = 0; j < 16; j++) {
                const float e0 = ex2(fmaf(s[4 * j], c_log2, -mc0));
                const float e1 = ex2(fmaf(s[4 * j + 1], c_log2, -mc0));
                const float e2 = ex2(fmaf(s[4 * j + 2], c_log2, -mc1));
                const float e3 = ex2(fmaf(s[4 * j + 3], c_log2, -mc1));
                x0 += e0; x1 += e1; x2 += e2; x3 += e3;
                p[2 * j] = pack_bf16(e0, e1);
                p[2 * j + 1] = pack_bf16(e2, e3);
            }
            r0 = x0 + x1;
            r1 = x2 + x3;
        };
        float x0, x1, x2, x3;
        auto exp_range = [&](uint32_t (&p)[32], auto J0, auto J1) {
            const float mc0 = m0 * c_log2, mc1 = m1 * c_log2;
#pragma unroll
            for (int j = decltype(J0)::value; j < decltype(J1)::value; j++) {
                const float e0 = ex2v(fmaf(s[4 * j], c_log2, -mc0));
                const float e1 = ex2v(fmaf(s[4 * j + 1], c_log2, -mc0));
                const float e2 = ex2v(fmaf(s[4 * j + 2], c_log2, -mc1));
                const float e3 = ex2v(fmaf(s[4 * j + 3], c_log2, -mc1));
                x0 += e0; x1 += e1; x2 += e2; x3 += e3;
                p[2 * j] = pack_bf16(e0, e1);
                p[2 * j + 1] = pack_bf16(e2, e3);
            }
        };
        auto store_o = [&](int buf, auto J0, auto J1) {
            const uint32_t ob = q_smem(buf, wg);
#pragma unroll
            for (int jj = decltype(J0)::value; jj < decltype(J1)::value; jj++) {
                stmatrix_x4(mat_addr(ob, jj),
                            pack_bf16(o[8 * jj] * inv0, o[8 * jj + 1] * inv0),
                            pack_bf16(o[8 * jj + 2] * inv1, o[8 * jj + 3] * inv1),
                            pack_bf16(o[8 * jj + 4] * inv0, o[8 * jj + 5] * inv0),
                            pack_bf16(o[8 * jj + 6] * inv1, o[8 * jj + 7] * inv1));
            }
        };
        auto publish_o = [&](bool pred) {
            asm volatile("{\n.reg .pred p;\nsetp.ne.u32 p, %1, 0;\n@p fence.proxy.async.shared::cta;\n"
                         "@p mbarrier.arrive.shared::cta.b64 _, [%0];\n}\n" :: "r"(oready_bar(wg)), "r"((uint32_t)pred) : "memory");
        };
        auto finish_l = [&](float x0, float x1) {
            x0 += __shfl_xor_sync(0xffffffffu, x0, 1);
            x1 += __shfl_xor_sync(0xffffffffu, x1, 1);
            x0 += __shfl_xor_sync(0xffffffffu, x0, 2);
            x1 += __shfl_xor_sync(0xffffffffu, x1, 2);
            inv0 = __fdividef(1.0f, x0); inv1 = __fdividef(1.0f, x1);
        };

        auto step = [&](auto Odd, int g, bool last, const uint32_t (&pin)[32], uint32_t (&pout)[32]) {
            constexpr bool ODD = decltype(Odd)::value;
            const int ti = g >> 2;
            const bool first_pv = ODD && ((g & 2) == 0);
            const bool boundary = !ODD && ((g & 2) == 0);
            const uint32_t kstage = ring.stage;
            ring.advance();
            const uint32_t vstage = ring.stage, vphase = ring.phase;
            ring.advance();
            named_sync(1 + wg, 256);
            STAMP(3);
            issue_qk(kstage, ti & 1);
            STAMP(4);
            if (first_pv && g > 1)
                store_o((ti - 1) & 1, IC<0>{}, IC<8>{});
            STAMP(1);
            mbar_wait(full_bar(vstage), vphase);
            STAMP(5);
            issue_pv(first_pv ? 0 : 1, vstage, pin);
            STAMP(6);
            if (wg == 0 || !last) named_arrive(1 + (wg ^ 1), 256);
            uint32_t ready = mbar_test(full_bar(ring.stage), ring.phase);
            const bool need_q = ODD && !first_pv && !last;
            STAMP(7);
            WG_WAIT(1);
            STAMP(8);
            release(kstage);
            x0 = x1 = x2 = x3 = 0.f;
            exp_range(pout, IC<0>{}, IC<JSPLIT>{});
            if (boundary) { finish_l(l0, l1); l0 = 0.f; l1 = 0.f; }
            if (ODD) publish_o(first_pv && g > 1);
            if (!ready) mbar_wait(full_bar(ring.stage), ring.phase);
            STAMP(9);
            WG_WAIT(0);
            release(vstage);
            if (ODD) ready = mbar_test(qfull_bar((ti + 1) & 1, wg), ((ti + 1) >> 1) & 1) | (need_q ? 0u : 1u);
            exp_range(pout, IC<JSPLIT>{}, IC<16>{});
            float r0 = x0 + x1, r1 = x2 + x3;
            const float lo = boundary ? SUM_LO : 0.f;
            const bool ok = (r0 <= SUM_HI) && (r1 <= SUM_HI) && (r0 >= lo) && (r1 >= lo);
            if (__builtin_expect(__any_sync(0xffffffffu, !ok), 0)) {
                float a0, a1;
                row_max(a0, a1);
                if (!boundary) {
                    a0 = fmaxf(m0, a0); a1 = fmaxf(m1, a1);
                    const float sc0 = ex2((m0 - a0) * c_log2), sc1 = ex2((m1 - a1) * c_log2);
                    l0 *= sc0; l1 *= sc1;
#pragma unroll
                    for (int i = 0; i < 16; i++) {
                        o[4 * i] *= sc0; o[4 * i + 1] *= sc0; o[4 * i + 2] *= sc1; o[4 * i + 3] *= sc1;
                    }
                }
                m0 = a0; m1 = a1;
                exp_pack(pout, r0, r1);
            }
            l0 += r0; l1 += r1;
            if (ODD && !ready) mbar_wait(qfull_bar((ti + 1) & 1, wg), ((ti + 1) >> 1) & 1);
            STAMP(12);
        };

        if (wg == 1) named_arrive(1, 256);
        PSTAMP(4);
        mbar_wait(qfull_bar(0, wg), 0);
        PSTAMP(5);
        mbar_wait(full_bar(ring.stage), ring.phase);
        PSTAMP(6);
        issue_qk(ring.stage, 0);
        WG_WAIT(0);
        PSTAMP(7);
        release(ring.stage);
        ring.advance();
        row_max(m0, m1);
        exp_pack(pa, l0, l1);
        PSTAMP(8);
        mbar_wait(full_bar(ring.stage), ring.phase);
        PSTAMP(9);

        SPANSTAMP(0);
        SPANSTAMP(1);
        const int G = my_tiles * NBLK;
        for (int g = 1; ; g += 2) {
            const bool last = (g + 1 == G);
            step(std::true_type{}, g, last, pa, pb);
            if (g < 8) PSTAMP(10 + (g >> 1));
            if (last) break;
            step(std::false_type{}, g + 1, false, pb, pa);
        }
        SPANSTAMP(2);
        issue_pv(1, ring.stage, pb);
        finish_l(l0, l1);
        WG_WAIT(0);
        release(ring.stage);
        store_o((my_tiles - 1) & 1, IC<0>{}, IC<8>{});
        publish_o(true);
        SPANSTAMP(3);
    }
}

typedef CUresult (*EncodeTiledFn)(CUtensorMap*, CUtensorMapDataType, cuuint32_t, void*, const cuuint64_t*,
                                  const cuuint64_t*, const cuuint32_t*, const cuuint32_t*, CUtensorMapInterleave,
                                  CUtensorMapSwizzle, CUtensorMapL2promotion, CUtensorMapFloatOOBfill);

void make_map(EncodeTiledFn fn, CUtensorMap* map, const void* ptr, uint64_t rows, uint32_t box_rows) {
    cuuint64_t dims[2] = {(cuuint64_t)D_HEAD, (cuuint64_t)rows};
    cuuint64_t strides[1] = {(cuuint64_t)D_HEAD * 2};
    cuuint32_t box[2] = {64, box_rows};
    cuuint32_t estr[2] = {1, 1};
    fn(map, CU_TENSOR_MAP_DATA_TYPE_BFLOAT16, 2, const_cast<void*>(ptr), dims, strides, box, estr,
       CU_TENSOR_MAP_INTERLEAVE_NONE, CU_TENSOR_MAP_SWIZZLE_128B, CU_TENSOR_MAP_L2_PROMOTION_L2_256B,
       CU_TENSOR_MAP_FLOAT_OOB_FILL_NONE);
}

}

extern "C" void kernel_launch(void* const* d_in, const int* in_sizes, int n_in, void* d_out, int out_size) {
    (void)in_sizes; (void)n_in; (void)out_size;
    static EncodeTiledFn encode = nullptr;
    if (!encode) {
        void* fn = nullptr;
        cudaDriverEntryPointQueryResult qres;
        cudaGetDriverEntryPoint("cuTensorMapEncodeTiled", &fn, cudaEnableDefault, &qres);
        encode = (EncodeTiledFn)fn;
        cudaFuncSetAttribute(gqa_attn_kernel, cudaFuncAttributeMaxDynamicSharedMemorySize, SMEM_TOTAL);
    }
    CUtensorMap mq, mk, mv, mo;
    make_map(encode, &mq, d_in[0], (uint64_t)NPAIRS * ROWS_PER_PAIR, 64);
    make_map(encode, &mk, d_in[1], (uint64_t)NPAIRS * SK, CLUSTER == 4 ? 64 : 128);
    make_map(encode, &mv, d_in[2], (uint64_t)NPAIRS * SK, CLUSTER == 4 ? 64 : 128);
    make_map(encode, &mo, d_out, (uint64_t)NPAIRS * ROWS_PER_PAIR, 64);

    cudaLaunchConfig_t cfg = {};
    cfg.gridDim = dim3(NUM_CTAS);
    cfg.blockDim = dim3(NTHREADS);
    cfg.dynamicSmemBytes = SMEM_TOTAL;
    cfg.stream = cudaStreamPerThread;
    cudaLaunchAttribute attr[1];
    attr[0].id = cudaLaunchAttributeClusterDimension;
    attr[0].val.clusterDim.x = CLUSTER;
    attr[0].val.clusterDim.y = 1;
    attr[0].val.clusterDim.z = 1;
    cfg.attrs = attr;
    cfg.numAttrs = 1;
    cudaLaunchKernelEx(&cfg, gqa_attn_kernel, mq, mk, mv, mo);
}
```

```cpp
#include <cuda_runtime.h>
#include <cuda_bf16.h>
#include <cuda.h>
#include <stdint.h>
#include <type_traits>

#define CLUSTER 2
#define PINGPONG 1
#define NUM_CTAS 128
#define JO 8
#define JE 9
#define PREFETCH 1

namespace {

constexpr int D_HEAD = 128;
constexpr int SK = 512;
constexpr int BM = 128;
constexpr int BN = 128;
constexpr int NBLK = SK / BN;
constexpr int ROWS_PER_PAIR = 2048;
constexpr int NPAIRS = 128;
constexpr int TILES_PER_PAIR = ROWS_PER_PAIR / BM;
constexpr int NTILES = NPAIRS * TILES_PER_PAIR;
constexpr int STAGES = 5;
constexpr int STAGE_BYTES = BN * D_HEAD * 2;
constexpr int QBUF_BYTES = BM * D_HEAD * 2;
constexpr int SMEM_Q = 0;
constexpr int SMEM_KV = 2 * QBUF_BYTES;
constexpr int SMEM_BAR = SMEM_KV + STAGES * STAGE_BYTES;
constexpr int SMEM_TOTAL = SMEM_BAR + 256 + 1024;
constexpr int NTHREADS = 384;

__device__ __forceinline__ uint32_t smem_u32(const void* p) { return (uint32_t)__cvta_generic_to_shared(p); }

__device__ __forceinline__ void mbar_init(uint32_t bar, uint32_t count) {
    asm volatile("mbarrier.init.shared::cta.b64 [%0], %1;\n" :: "r"(bar), "r"(count) : "memory");
}
__device__ __forceinline__ void mbar_expect_tx(uint32_t bar, uint32_t bytes) {
    asm volatile("mbarrier.arrive.expect_tx.shared::cta.b64 _, [%0], %1;\n" :: "r"(bar), "r"(bytes) : "memory");
}
__device__ __forceinline__ void mbar_arrive_cluster(uint32_t bar, uint32_t cta) {
    asm volatile("{\n.reg .b32 ra;\nmapa.shared::cluster.u32 ra, %0, %1;\n"
                 "mbarrier.arrive.shared::cluster.b64 _, [ra];\n}\n" :: "r"(bar), "r"(cta) : "memory");
}
[[maybe_unused]] __device__ __forceinline__ void mbar_arrive_local(uint32_t bar) {
    asm volatile("mbarrier.arrive.shared::cta.b64 _, [%0];\n" :: "r"(bar) : "memory");
}
__device__ __forceinline__ void mbar_wait(uint32_t bar, uint32_t parity) {
    asm volatile("{\n.reg .pred p, q;\n.reg .u32 c;\nmov.u32 c, 0;\n"
                 "LAB_WAIT:\n"
                 "mbarrier.try_wait.parity.shared::cta.b64 p, [%0], %1;\n"
                 "@p bra LAB_DONE;\n"
                 "add.u32 c, c, 1;\n"
                 "setp.gt.u32 q, c, 16777216;\n"
                 "@q trap;\n"
                 "bra LAB_WAIT;\n"
                 "LAB_DONE:\n}\n" :: "r"(bar), "r"(parity) : "memory");
}
__device__ __forceinline__ uint32_t mbar_test(uint32_t bar, uint32_t parity) {
    uint32_t ok;
    asm volatile("{\n.reg .pred p;\nmbarrier.test_wait.parity.shared::cta.b64 p, [%1], %2;\nselp.u32 %0, 1, 0, p;\n}\n"
                 : "=r"(ok) : "r"(bar), "r"(parity) : "memory");
    return ok;
}

__device__ __forceinline__ void tma_load_2d(uint32_t dst, const CUtensorMap* map, int c0, int c1, uint32_t bar) {
    asm volatile("cp.async.bulk.tensor.2d.shared::cluster.global.mbarrier::complete_tx::bytes [%0], [%1, {%3, %4}], [%2];\n"
                 :: "r"(dst), "l"(map), "r"(bar), "r"(c0), "r"(c1) : "memory");
}
__device__ __forceinline__ void tma_load_2d_mc(uint32_t dst, const CUtensorMap* map, int c0, int c1, uint32_t bar, uint16_t mask) {
    asm volatile("cp.async.bulk.tensor.2d.shared::cluster.global.mbarrier::complete_tx::bytes.multicast::cluster [%0], [%1, {%3, %4}], [%2], %5;\n"
                 :: "r"(dst), "l"(map), "r"(bar), "r"(c0), "r"(c1), "h"(mask) : "memory");
}
__device__ __forceinline__ void tma_store_2d(const CUtensorMap* map, uint32_t src, int c0, int c1) {
    asm volatile("cp.async.bulk.tensor.2d.global.shared::cta.bulk_group [%0, {%2, %3}], [%1];\n"
                 :: "l"(map), "r"(src), "r"(c0), "r"(c1) : "memory");
}
__device__ __forceinline__ void tma_prefetch_2d(const CUtensorMap* map, int c0, int c1) {
    asm volatile("cp.async.bulk.prefetch.tensor.2d.L2.global [%0, {%1, %2}];\n"
                 :: "l"(map), "r"(c0), "r"(c1) : "memory");
}

#define WG_FENCE() asm volatile("wgmma.fence.sync.aligned;\n" ::: "memory")
#define WG_COMMIT() asm volatile("wgmma.commit_group.sync.aligned;\n" ::: "memory")
#define WG_WAIT(n) asm volatile("wgmma.wait_group.sync.aligned " #n ";\n" ::: "memory")

#define ACC64(d) \
  "+f"(d[0]), "+f"(d[1]), "+f"(d[2]), "+f"(d[3]), "+f"(d[4]), "+f"(d[5]), "+f"(d[6]), "+f"(d[7]), \
  "+f"(d[8]), "+f"(d[9]), "+f"(d[10]), "+f"(d[11]), "+f"(d[12]), "+f"(d[13]), "+f"(d[14]), "+f"(d[15]), \
  "+f"(d[16]), "+f"(d[17]), "+f"(d[18]), "+f"(d[19]), "+f"(d[20]), "+f"(d[21]), "+f"(d[22]), "+f"(d[23]), \
  "+f"(d[24]), "+f"(d[25]), "+f"(d[26]), "+f"(d[27]), "+f"(d[28]), "+f"(d[29]), "+f"(d[30]), "+f"(d[31]), \
  "+f"(d[32]), "+f"(d[33]), "+f"(d[34]), "+f"(d[35]), "+f"(d[36]), "+f"(d[37]), "+f"(d[38]), "+f"(d[39]), \
  "+f"(d[40]), "+f"(d[41]), "+f"(d[42]), "+f"(d[43]), "+f"(d[44]), "+f"(d[45]), "+f"(d[46]), "+f"(d[47]), \
  "+f"(d[48]), "+f"(d[49]), "+f"(d[50]), "+f"(d[51]), "+f"(d[52]), "+f"(d[53]), "+f"(d[54]), "+f"(d[55]), \
  "+f"(d[56]), "+f"(d[57]), "+f"(d[58]), "+f"(d[59]), "+f"(d[60]), "+f"(d[61]), "+f"(d[62]), "+f"(d[63])
#define REGS64 \
  "{%0, %1, %2, %3, %4, %5, %6, %7, %8, %9, %10, %11, %12, %13, %14, %15, " \
  "%16, %17, %18, %19, %20, %21, %22, %23, %24, %25, %26, %27, %28, %29, %30, %31, " \
  "%32, %33, %34, %35, %36, %37, %38, %39, %40, %41, %42, %43, %44, %45, %46, %47, " \
  "%48, %49, %50, %51, %52, %53, %54, %55, %56, %57, %58, %59, %60, %61, %62, %63}"

template <int SCALE_D>
__device__ __forceinline__ void wgmma_ss(float (&d)[64], uint32_t da_lo, uint32_t db_lo) {
    if constexpr (SCALE_D) {
        asm volatile("{\n.reg .b64 da, db;\nmov.b64 da, {%64, %66};\nmov.b64 db, {%65, %66};\n"
                     "wgmma.mma_async.sync.aligned.m64n128k16.f32.bf16.bf16 " REGS64 ", da, db, 1, 1, 1, 0, 0;\n}\n"
                     : ACC64(d) : "r"(da_lo), "r"(db_lo), "r"(0x40000040));
    } else {
        asm volatile("{\n.reg .b64 da, db;\nmov.b64 da, {%64, %66};\nmov.b64 db, {%65, %66};\n"
                     "wgmma.mma_async.sync.aligned.m64n128k16.f32.bf16.bf16 " REGS64 ", da, db, 0, 1, 1, 0, 0;\n}\n"
                     : ACC64(d) : "r"(da_lo), "r"(db_lo), "r"(0x40000040));
    }
}
template <int SCALE_D, int TB>
__device__ __forceinline__ void wgmma_rs(float (&d)[64], uint32_t a0, uint32_t a1, uint32_t a2, uint32_t a3,
                                         uint32_t db_lo) {
    if constexpr (SCALE_D) {
        asm volatile("{\n.reg .b64 db;\nmov.b64 db, {%68, %70};\n"
                     "wgmma.mma_async.sync.aligned.m64n128k16.f32.bf16.bf16 " REGS64 ", {%64, %65, %66, %67}, db, 1, 1, 1, %69;\n}\n"
                     : ACC64(d) : "r"(a0), "r"(a1), "r"(a2), "r"(a3), "r"(db_lo), "n"(TB), "r"(0x40000040));
    } else {
        asm volatile("{\n.reg .b64 db;\nmov.b64 db, {%68, %70};\n"
                     "wgmma.mma_async.sync.aligned.m64n128k16.f32.bf16.bf16 " REGS64 ", {%64, %65, %66, %67}, db, 0, 1, 1, %69;\n}\n"
                     : ACC64(d) : "r"(a0), "r"(a1), "r"(a2), "r"(a3), "r"(db_lo), "n"(TB), "r"(0x40000040));
    }
}

template <int TB>
__device__ __forceinline__ void wgmma_rs_p(float (&d)[64], uint32_t a0, uint32_t a1, uint32_t a2, uint32_t a3,
                                           uint32_t db_lo, int scale_d) {
    asm volatile("{\n.reg .b64 db;\n.reg .pred p;\nsetp.ne.b32 p, %71, 0;\nmov.b64 db, {%68, %70};\n"
                 "wgmma.mma_async.sync.aligned.m64n128k16.f32.bf16.bf16 " REGS64 ", {%64, %65, %66, %67}, db, p, 1, 1, %69;\n}\n"
                 : ACC64(d) : "r"(a0), "r"(a1), "r"(a2), "r"(a3), "r"(db_lo), "n"(TB), "r"(0x40000040), "r"(scale_d));
}

__device__ __forceinline__ uint32_t pack_bf16(float lo, float hi) {
    uint32_t r;
    asm("cvt.rn.bf16x2.f32 %0, %1, %2;\n" : "=r"(r) : "f"(hi), "f"(lo));
    return r;
}
__device__ __forceinline__ float ex2(float x) {
    float y;
    asm("ex2.approx.ftz.f32 %0, %1;\n" : "=f"(y) : "f"(x));
    return y;
}
__device__ __forceinline__ float ex2v(float x) {
    float y;
    asm volatile("ex2.approx.ftz.f32 %0, %1;\n" : "=f"(y) : "f"(x));
    return y;
}
__device__ __forceinline__ void named_sync(int id, int n) { asm volatile("bar.sync %0, %1;\n" :: "r"(id), "r"(n) : "memory"); }
__device__ __forceinline__ void named_arrive(int id, int n) { asm volatile("bar.arrive %0, %1;\n" :: "r"(id), "r"(n) : "memory"); }

__device__ __forceinline__ void stmatrix_x4(uint32_t addr, uint32_t r0, uint32_t r1, uint32_t r2, uint32_t r3) {
    asm volatile("stmatrix.sync.aligned.m8n8.x4.shared.b16 [%0], {%1, %2, %3, %4};\n"
                 :: "r"(addr), "r"(r0), "r"(r1), "r"(r2), "r"(r3) : "memory");
}

template <int V> using IC = std::integral_constant<int, V>;

struct Ring {
    uint32_t stage, phase;
    __device__ __forceinline__ void advance() { if (++stage == STAGES) { stage = 0; phase ^= 1; } }
};

__global__ void __launch_bounds__(NTHREADS, 1)
gqa_attn_kernel(const __grid_constant__ CUtensorMap map_q, const __grid_constant__ CUtensorMap map_k,
                const __grid_constant__ CUtensorMap map_v, const __grid_constant__ CUtensorMap map_o) {
    extern __shared__ uint8_t smem_raw[];
    const uint32_t sbase = (smem_u32(smem_raw) + 1023u) & ~1023u;
    const uint32_t bar_base = sbase + SMEM_BAR;
    auto full_bar = [&](uint32_t s) { return bar_base + s * 8; };
    auto empty_bar = [&](uint32_t s) { return bar_base + 64 + s * 8; };
    auto qfull_bar = [&](uint32_t buf, uint32_t wg) { return bar_base + 128 + (buf * 2 + wg) * 8; };
    auto oready_bar = [&](uint32_t wg) { return bar_base + 160 + wg * 8; };

    const int tid = threadIdx.x;
    const int wg_idx = __shfl_sync(0xffffffffu, tid >> 7, 0);
    uint32_t cta_rank = 0;
    asm volatile("mov.u32 %0, %%cluster_ctarank;\n" : "=r"(cta_rank));
    const int cluster_id = blockIdx.x / CLUSTER;
    const int num_clusters = gridDim.x / CLUSTER;
    constexpr int NCT = NTILES / CLUSTER;
    const int my_tiles = (NCT - cluster_id + num_clusters - 1) / num_clusters;

    auto q_smem = [&](int buf, int wg) { return sbase + SMEM_Q + buf * QBUF_BYTES + wg * 16384; };
    auto tile_row = [&](int i, int wg) {
        const int ct = cluster_id + i * num_clusters;
        return (ct * CLUSTER + (int)cta_rank) * BM + wg * 64;
    };
    auto load_q = [&](int i, int wg) {
        const int buf = i & 1;
        const uint32_t fb = qfull_bar(buf, wg);
        mbar_expect_tx(fb, 16384);
        tma_load_2d(q_smem(buf, wg), &map_q, 0, tile_row(i, wg), fb);
        tma_load_2d(q_smem(buf, wg) + 8192, &map_q, 64, tile_row(i, wg), fb);
    };

    auto prefetch_kv = [&](int ti) {
        if (ti < my_tiles) {
            const int nt = (cluster_id + ti * num_clusters) * CLUSTER + (int)cta_rank;
            const int idx = nt & (TILES_PER_PAIR - 1);
            tma_prefetch_2d((idx & 2) ? &map_v : &map_k, (idx & 1) * 64, (nt / TILES_PER_PAIR) * SK + (idx >> 2) * BN);
        }
    };

    if (tid == 256) {
        for (int s = 0; s < STAGES; s++) {
            mbar_init(full_bar(s), 1);
            mbar_init(empty_bar(s), 2 * CLUSTER);
        }
        for (int i = 0; i < 4; i++) mbar_init(bar_base + 128 + i * 8, 1);
        mbar_init(oready_bar(0), 128);
        mbar_init(oready_bar(1), 128);
        asm volatile("fence.mbarrier_init.release.cluster;\n" ::: "memory");
        asm volatile("fence.proxy.async.shared::cta;\n" ::: "memory");
        load_q(0, 0);
        const int row0 = ((cluster_id * CLUSTER) / TILES_PER_PAIR) * SK;
#pragma unroll 1
        for (int n = 0; n < STAGES; n++) {
            const bool is_v = (n == 2) || (n == 4);
            const CUtensorMap* map = is_v ? &map_v : &map_k;
            const int row = row0 + (is_v ? (n >> 1) - 1 : (n + 1) >> 1) * BN;
            mbar_expect_tx(full_bar(n), STAGE_BYTES);
            tma_load_2d(sbase + SMEM_KV + n * STAGE_BYTES, map, 0, row, full_bar(n));
            tma_load_2d(sbase + SMEM_KV + n * STAGE_BYTES + 16384, map, 64, row, full_bar(n));
            if (n == 0) load_q(0, 1);
        }
    } else if (tid == 320) {
        asm volatile("prefetch.tensormap [%0];\n" :: "l"(&map_k) : "memory");
        asm volatile("prefetch.tensormap [%0];\n" :: "l"(&map_v) : "memory");
        asm volatile("prefetch.tensormap [%0];\n" :: "l"(&map_o) : "memory");
    }
    __syncthreads();
    asm volatile("barrier.cluster.arrive.relaxed.aligned;\nbarrier.cluster.wait.aligned;\n" ::: "memory");

    if (wg_idx == 2) {
        asm volatile("setmaxnreg.dec.sync.aligned.u32 24;\n");
        if (tid == 256) {
            const int G = my_tiles * NBLK;
            Ring ring{0, 0};
            auto load_kv = [&](const CUtensorMap* map, int g) {
                const int ct = cluster_id + (g >> 2) * num_clusters;
                const int pair = (ct * CLUSTER) / TILES_PER_PAIR;
                const int row = pair * SK + (g & 3) * BN;
                mbar_wait(empty_bar(ring.stage), ring.phase);
                const uint32_t fb = full_bar(ring.stage);
                mbar_expect_tx(fb, STAGE_BYTES);
                const uint32_t dst = sbase + SMEM_KV + ring.stage * STAGE_BYTES;
                tma_load_2d_mc(dst + cta_rank * 16384, map, cta_rank * 64, row, fb, (uint16_t)3);
                ring.advance();
            };
            for (int g = 3; g < G; g++) {
                load_kv(&map_k, g);
                if (g == 3 && my_tiles > 1) {
                    prefetch_kv(1);
                    load_q(1, 0);
                    load_q(1, 1);
                }
                load_kv(&map_v, g - 1);
                if ((g & 3) == PREFETCH) prefetch_kv((g >> 2) + 1);
            }
            load_kv(&map_v, G - 1);
            for (int s = 0; s < STAGES; s++) {
                mbar_wait(empty_bar(ring.stage), ring.phase);
                ring.advance();
            }
        } else if (tid == 288 || tid == 320) {
            const int wg = (tid - 288) >> 5;
            for (int i = 0; i < my_tiles; i++) {
                mbar_wait(oready_bar(wg), i & 1);
                tma_store_2d(&map_o, q_smem(i & 1, wg), 0, tile_row(i, wg));
                tma_store_2d(&map_o, q_smem(i & 1, wg) + 8192, 64, tile_row(i, wg));
                asm volatile("cp.async.bulk.commit_group;\n" ::: "memory");
                if (i + 2 < my_tiles) {
                    asm volatile("cp.async.bulk.wait_group.read 0;\n" ::: "memory");
                    load_q(i + 2, wg);
                }
            }
            asm volatile("cp.async.bulk.wait_group 0;\n" ::: "memory");
        }
    } else {
        asm volatile("setmaxnreg.inc.sync.aligned.u32 240;\n");
        const int wg = wg_idx;
        const int t = tid & 127;
        const int warp = t >> 5, lane = t & 31;
        const float c_log2 = 0.08838834764831845f * 1.4426950408889634f;
        const float SUM_HI = 1073741824.0f, SUM_LO = 1.0f / 1073741824.0f;

        auto release = [&](uint32_t stage) {
            if (t < CLUSTER) mbar_arrive_cluster(empty_bar(stage), t);
        };

        const int mrow = warp * 16 + (lane & 7) + ((lane >> 3) & 1) * 8;
        const uint32_t mat_off = mrow * 128;
        const uint32_t mat_x = (uint32_t)(lane >> 4);
        const uint32_t mat_sw = (uint32_t)(lane & 7);
        auto mat_addr = [&](uint32_t base, int kk) {
            return base + (kk >> 2) * 8192 + mat_off + ((((kk & 3) * 2 + mat_x) ^ mat_sw) << 4);
        };

        float s[64], o[64];
        uint32_t pa[32], pb[32];
        float m0 = 0.f, m1 = 0.f, l0 = 0.f, l1 = 0.f;
        float inv0 = 0.f, inv1 = 0.f;
        Ring ring{0, 0};
        const uint32_t kv_desc0 = ((sbase + SMEM_KV) & 0x3FFFF) >> 4;
        const uint32_t q_desc0 = ((q_smem(0, wg) & 0x3FFFF) >> 4) | (1u << 16);

        auto issue_qk = [&](uint32_t stage, int qbuf) {
            const uint32_t db = (kv_desc0 + stage * (STAGE_BYTES >> 4)) | (1u << 16);
            const uint32_t da = q_desc0 + qbuf * (QBUF_BYTES >> 4);
            WG_FENCE();
            wgmma_ss<0>(s, da, db);
#pragma unroll
            for (int kk = 1; kk < 8; kk++)
                wgmma_ss<1>(s, da + (kk >> 2) * 512 + (kk & 3) * 2, db + (kk >> 2) * 1024 + (kk & 3) * 2);
            WG_COMMIT();
        };
        auto issue_pv = [&](int accumulate, uint32_t stage, const uint32_t (&p)[32]) {
            const uint32_t db = (kv_desc0 + stage * (STAGE_BYTES >> 4)) | (1024u << 16);
            WG_FENCE();
            wgmma_rs_p<1>(o, p[0], p[1], p[2], p[3], db, accumulate);
#pragma unroll
            for (int kk = 1; kk < 8; kk++)
                wgmma_rs<1, 1>(o, p[kk * 4], p[kk * 4 + 1], p[kk * 4 + 2], p[kk * 4 + 3], db + kk * 128);
            WG_COMMIT();
        };
        auto row_max = [&](float& a0, float& a1) {
            a0 = fmaxf(s[0], s[1]); a1 = fmaxf(s[2], s[3]);
            float b0 = fmaxf(s[4], s[5]), b1 = fmaxf(s[6], s[7]);
#pragma unroll
            for (int j = 2; j < 16; j += 2) {
                a0 = fmaxf(a0, fmaxf(s[4 * j], s[4 * j + 1]));
                a1 = fmaxf(a1, fmaxf(s[4 * j + 2], s[4 * j + 3]));
                b0 = fmaxf(b0, fmaxf(s[4 * j + 4], s[4 * j + 5]));
                b1 = fmaxf(b1, fmaxf(s[4 * j + 6], s[4 * j + 7]));
            }
            a0 = fmaxf(a0, b0); a1 = fmaxf(a1, b1);
            a0 = fmaxf(a0, __shfl_xor_sync(0xffffffffu, a0, 1));
            a1 = fmaxf(a1, __shfl_xor_sync(0xffffffffu, a1, 1));
            a0 = fmaxf(a0, __shfl_xor_sync(0xffffffffu, a0, 2));
            a1 = fmaxf(a1, __shfl_xor_sync(0xffffffffu, a1, 2));
        };
        auto exp_pack = [&](uint32_t (&p)[32], float& r0, float& r1) {
            const float mc0 = m0 * c_log2, mc1 = m1 * c_log2;
            float x0 = 0.f, x1 = 0.f, x2 = 0.f, x3 = 0.f;
#pragma unroll
            for (int j = 0; j < 16; j++) {
                const float e0 = ex2(fmaf(s[4 * j], c_log2, -mc0));
                const float e1 = ex2(fmaf(s[4 * j + 1], c_log2, -mc0));
                const float e2 = ex2(fmaf(s[4 * j + 2], c_log2, -mc1));
                const float e3 = ex2(fmaf(s[4 * j + 3], c_log2, -mc1));
                x0 += e0; x1 += e1; x2 += e2; x3 += e3;
                p[2 * j] = pack_bf16(e0, e1);
                p[2 * j + 1] = pack_bf16(e2, e3);
            }
            r0 = x0 + x1;
            r1 = x2 + x3;
        };
        float x0, x1, x2, x3;
        auto exp_range = [&](uint32_t (&p)[32], auto J0, auto J1) {
            const float mc0 = m0 * c_log2, mc1 = m1 * c_log2;
#pragma unroll
            for (int j = decltype(J0)::value; j < decltype(J1)::value; j++) {
                const float e0 = ex2v(fmaf(s[4 * j], c_log2, -mc0));
                const float e1 = ex2v(fmaf(s[4 * j + 1], c_log2, -mc0));
                const float e2 = ex2v(fmaf(s[4 * j + 2], c_log2, -mc1));
                const float e3 = ex2v(fmaf(s[4 * j + 3], c_log2, -mc1));
                x0 += e0; x1 += e1; x2 += e2; x3 += e3;
                p[2 * j] = pack_bf16(e0, e1);
                p[2 * j + 1] = pack_bf16(e2, e3);
            }
        };
        auto store_o = [&](int buf, auto J0, auto J1) {
            const uint32_t ob = q_smem(buf, wg);
#pragma unroll
            for (int jj = decltype(J0)::value; jj < decltype(J1)::value; jj++) {
                stmatrix_x4(mat_addr(ob, jj),
                            pack_bf16(o[8 * jj] * inv0, o[8 * jj + 1] * inv0),
                            pack_bf16(o[8 * jj + 2] * inv1, o[8 * jj + 3] * inv1),
                            pack_bf16(o[8 * jj + 4] * inv0, o[8 * jj + 5] * inv0),
                            pack_bf16(o[8 * jj + 6] * inv1, o[8 * jj + 7] * inv1));
            }
        };
        auto publish_o = [&](bool pred) {
            asm volatile("{\n.reg .pred p;\nsetp.ne.u32 p, %1, 0;\n@p fence.proxy.async.shared::cta;\n"
                         "@p mbarrier.arrive.shared::cta.b64 _, [%0];\n}\n" :: "r"(oready_bar(wg)), "r"((uint32_t)pred) : "memory");
        };
        auto finish_l = [&](float x0, float x1) {
            x0 += __shfl_xor_sync(0xffffffffu, x0, 1);
            x1 += __shfl_xor_sync(0xffffffffu, x1, 1);
            x0 += __shfl_xor_sync(0xffffffffu, x0, 2);
            x1 += __shfl_xor_sync(0xffffffffu, x1, 2);
            inv0 = __fdividef(1.0f, x0); inv1 = __fdividef(1.0f, x1);
        };

        auto step = [&](auto Odd, int g, bool last, const uint32_t (&pin)[32], uint32_t (&pout)[32]) {
            constexpr bool ODD = decltype(Odd)::value;
            const int ti = g >> 2;
            const bool first_pv = ODD && ((g & 2) == 0);
            const bool boundary = !ODD && ((g & 2) == 0);
            const uint32_t kstage = ring.stage;
            ring.advance();
            const uint32_t vstage = ring.stage, vphase = ring.phase;
            ring.advance();
            named_sync(1 + wg, 256);
            issue_qk(kstage, ti & 1);
            if (first_pv && g > 1)
                store_o((ti - 1) & 1, IC<0>{}, IC<8>{});
            mbar_wait(full_bar(vstage), vphase);
            issue_pv(first_pv ? 0 : 1, vstage, pin);
            if (wg == 0 || !last) named_arrive(1 + (wg ^ 1), 256);
            uint32_t ready = mbar_test(full_bar(ring.stage), ring.phase);
            const bool need_q = ODD && !first_pv && !last;
            WG_WAIT(1);
            release(kstage);
            x0 = x1 = x2 = x3 = 0.f;
            exp_range(pout, IC<0>{}, IC<(ODD ? JO : JE)>{});
            if (boundary) { finish_l(l0, l1); l0 = 0.f; l1 = 0.f; }
            if (ODD) publish_o(first_pv && g > 1);
            if (!ready) mbar_wait(full_bar(ring.stage), ring.phase);
            WG_WAIT(0);
            release(vstage);
            if (ODD) ready = mbar_test(qfull_bar((ti + 1) & 1, wg), ((ti + 1) >> 1) & 1) | (need_q ? 0u : 1u);
            exp_range(pout, IC<(ODD ? JO : JE)>{}, IC<16>{});
            float r0 = x0 + x1, r1 = x2 + x3;
            const float lo = boundary ? SUM_LO : 0.f;
            const bool ok = (r0 <= SUM_HI) && (r1 <= SUM_HI) && (r0 >= lo) && (r1 >= lo);
            if (__builtin_expect(__any_sync(0xffffffffu, !ok), 0)) {
                float a0, a1;
                row_max(a0, a1);
                if (!boundary) {
                    a0 = fmaxf(m0, a0); a1 = fmaxf(m1, a1);
                    const float sc0 = ex2((m0 - a0) * c_log2), sc1 = ex2((m1 - a1) * c_log2);
                    l0 *= sc0; l1 *= sc1;
#pragma unroll
                    for (int i = 0; i < 16; i++) {
                        o[4 * i] *= sc0; o[4 * i + 1] *= sc0; o[4 * i + 2] *= sc1; o[4 * i + 3] *= sc1;
                    }
                }
                m0 = a0; m1 = a1;
                exp_pack(pout, r0, r1);
            }
            l0 += r0; l1 += r1;
            if (ODD && !ready) mbar_wait(qfull_bar((ti + 1) & 1, wg), ((ti + 1) >> 1) & 1);
        };

        if (wg == 1) named_arrive(1, 256);
        mbar_wait(qfull_bar(0, wg), 0);
        mbar_wait(full_bar(ring.stage), ring.phase);
        issue_qk(ring.stage, 0);
        WG_WAIT(0);
        release(ring.stage);
        ring.advance();
        row_max(m0, m1);
        exp_pack(pa, l0, l1);
        mbar_wait(full_bar(ring.stage), ring.phase);
        const int G = my_tiles * NBLK;
        for (int g = 1; ; g += 2) {
            const bool last = (g + 1 == G);
            step(std::true_type{}, g, last, pa, pb);
            if (last) break;
            step(std::false_type{}, g + 1, false, pb, pa);
        }
        issue_pv(1, ring.stage, pb);
        finish_l(l0, l1);
        WG_WAIT(0);
        release(ring.stage);
        store_o((my_tiles - 1) & 1, IC<0>{}, IC<8>{});
        publish_o(true);
    }
}

typedef CUresult (*EncodeTiledFn)(CUtensorMap*, CUtensorMapDataType, cuuint32_t, void*, const cuuint64_t*,
                                  const cuuint64_t*, const cuuint32_t*, const cuuint32_t*, CUtensorMapInterleave,
                                  CUtensorMapSwizzle, CUtensorMapL2promotion, CUtensorMapFloatOOBfill);

void make_map(EncodeTiledFn fn, CUtensorMap* map, const void* ptr, uint64_t rows, uint32_t box_rows) {
    cuuint64_t dims[2] = {(cuuint64_t)D_HEAD, (cuuint64_t)rows};
    cuuint64_t strides[1] = {(cuuint64_t)D_HEAD * 2};
    cuuint32_t box[2] = {64, box_rows};
    cuuint32_t estr[2] = {1, 1};
    fn(map, CU_TENSOR_MAP_DATA_TYPE_BFLOAT16, 2, const_cast<void*>(ptr), dims, strides, box, estr,
       CU_TENSOR_MAP_INTERLEAVE_NONE, CU_TENSOR_MAP_SWIZZLE_128B, CU_TENSOR_MAP_L2_PROMOTION_L2_256B,
       CU_TENSOR_MAP_FLOAT_OOB_FILL_NONE);
}

}

extern "C" void kernel_launch(void* const* d_in, const int* in_sizes, int n_in, void* d_out, int out_size) {
    (void)in_sizes; (void)n_in; (void)out_size;
    static EncodeTiledFn encode = nullptr;
    if (!encode) {
        void* fn = nullptr;
        cudaDriverEntryPointQueryResult qres;
        cudaGetDriverEntryPoint("cuTensorMapEncodeTiled", &fn, cudaEnableDefault, &qres);
        encode = (EncodeTiledFn)fn;
        cudaFuncSetAttribute(gqa_attn_kernel, cudaFuncAttributeMaxDynamicSharedMemorySize, SMEM_TOTAL);
    }
    CUtensorMap mq, mk, mv, mo;
    make_map(encode, &mq, d_in[0], (uint64_t)NPAIRS * ROWS_PER_PAIR, 64);
    make_map(encode, &mk, d_in[1], (uint64_t)NPAIRS * SK, 128);
    make_map(encode, &mv, d_in[2], (uint64_t)NPAIRS * SK, 128);
    make_map(encode, &mo, d_out, (uint64_t)NPAIRS * ROWS_PER_PAIR, 64);

    cudaLaunchConfig_t cfg = {};
    cfg.gridDim = dim3(NUM_CTAS);
    cfg.blockDim = dim3(NTHREADS);
    cfg.dynamicSmemBytes = SMEM_TOTAL;
    cfg.stream = cudaStreamPerThread;
    cudaLaunchAttribute attr[1];
    attr[0].id = cudaLaunchAttributeClusterDimension;
    attr[0].val.clusterDim.x = CLUSTER;
    attr[0].val.clusterDim.y = 1;
    attr[0].val.clusterDim.z = 1;
    cfg.attrs = attr;
    cfg.numAttrs = 1;
    cudaLaunchKernelEx(&cfg, gqa_attn_kernel, mq, mk, mv, mo);
}
```
